```python
import torch

def _softmax(x, axis=-1):
    return torch.softmax(x, dim=axis)
def _gelu(x):
    return torch.nn.functional.gelu(x, approximate="tanh")
def _silu(x):
    return torch.nn.functional.silu(x)
def _sigmoid(x):
    return torch.sigmoid(x)
def _layernorm(x, axis=-1, eps=1e-5):
    m = x.mean(dim=axis, keepdim=True)
    v = x.var(dim=axis, keepdim=True, unbiased=False)
    return (x - m) / torch.sqrt(v + eps)
def _scatter_add(tgt, idx, src, axis=0):
    return tgt.clone().index_add_(axis, idx, src)
def _segment_sum(src, seg, n):
    out = torch.zeros((n,) + src.shape[1:], dtype=src.dtype)
    return out.index_add_(0, seg, src)
def _pad(x, pw):
    flat = tuple(v for pair in reversed(pw) for v in pair)
    return torch.nn.functional.pad(x, flat)

kernel_name = 'standalone__geglu_ffn__prompt'

def setup_inputs():

    _w = (lambda a: (lambda t: t.to(torch.bfloat16) if t.is_floating_point() else t)(torch.as_tensor(a)))
    B, S, D, F = 1, 2048, 1024, 3584
    return {
        "x": _w((lambda *s: torch.randn(*s, dtype=torch.bfloat16) * 0.05)(B, S, D)),
        "w_gate": _w((lambda *s: torch.randn(*s, dtype=torch.bfloat16) * 0.05)(D, F)),
        "w_up": _w((lambda *s: torch.randn(*s, dtype=torch.bfloat16) * 0.05)(D, F)),
        "w_down": _w((lambda *s: torch.randn(*s, dtype=torch.bfloat16) * 0.05)(F, D)),
    }

def reference(x, w_gate, w_up, w_down):
    return (_gelu(x @ w_gate) * (x @ w_up)) @ w_down
```

```cpp
#include <cuda_runtime.h>
#include <cuda_bf16.h>
#include <cuda.h>
#include <stdint.h>

namespace {

constexpr int kM = 2048, kD = 1024, kF = 3584;
constexpr int kAtoms = kF / 64;
constexpr uint32_t kRing = 196608, kBig = 49152, kSmall = 32768, kStg = 32768;
constexpr uint32_t kSmemBytes = kRing + kStg + 256;
constexpr int kG2a = 16;
constexpr int kTailKb = 5, kTailRs = 4, kHalfEpi = 1;
constexpr unsigned kStoreGap = 100, kPollGap = 128;
constexpr int kT2 = 40 * 64, kXCol = 54 * 64;

__host__ __device__ constexpr int ph_n(int p) { return p == 3 ? kG2a : p == 5 ? kAtoms - kG2a : 16; }
__host__ __device__ constexpr int ph_len(int p) { return (p & 1) ? 2 : 3; }
__host__ __device__ constexpr int ph_stages(int p) { return 12 / ph_len(p); }
__host__ __device__ constexpr int ph_first(int p) { return p == 0 ? 0 : ph_first(p - 1) + ph_n(p - 1); }
__host__ __device__ constexpr int ph_start(int p, bool z) {
  if (p == 0 || (z && p == 2)) return 0;
  if (z && p == 5) return 4;
  int last = (ph_start(p - 1, z) + ph_n(p - 1) - 1) % ph_stages(p - 1);
  int end = (last + 1) * ph_len(p - 1);
  return ((end + ph_len(p) - 1) / ph_len(p)) % ph_stages(p);
}
__host__ __device__ constexpr int kb_phase(int i) { int p = 0; while (i >= ph_first(p) + ph_n(p)) p++; return p; }
__host__ __device__ constexpr int kb_lo(int i, bool z) {
  int p = kb_phase(i);
  if (z && p == 4) return (8 + 3 * (i - ph_first(p))) % 12;
  return ((ph_start(p, z) + i - ph_first(p)) % ph_stages(p)) * ph_len(p);
}
template <bool Z> __host__ __device__ constexpr uint32_t kb_off(int i) {
  constexpr int d = ph_start(5, Z) - ph_first(5);
  return ((i + d) % 6) * 32768u;
}
__host__ __device__ constexpr int kb_hi(int i, bool z) { return kb_lo(i, z) + ph_len(kb_phase(i)); }
__host__ __device__ constexpr int nib(int i, uint64_t lo, uint64_t hi) { return (int)(((i & 16) ? hi : lo) >> (4 * (i & 15))) & 15; }
__host__ __device__ constexpr int blk_a(int i) { return nib(i, 0x9630963096DC96DCull, 0x963047DC963096DCull); }
__host__ __device__ constexpr int blk_b(int i) { return nib(i, 0xBA8741A75421A741ull, 0x87BA5821A741A741ull); }
__host__ __device__ constexpr int blk_k(int i) { return nib(i, 0x7654765432103210ull, 0xFEDCBA98FEDCBA98ull); }
__host__ __device__ constexpr int blk_units(int i) { return nib(i, 0x1111333311113333ull, 0x1111221133333333ull); }
constexpr uint32_t ph_deltas(int p, bool z) {
  if (z && p == 2) return 0x6367;
  if (z && p >= 4) return ph_deltas(p, false);
  uint32_t d = 0;
  for (int t = 0; t < ph_stages(p); t++) {
    int i = ph_first(p) + t, delta = 0;
    for (int j = i - 1; j >= 0; j--)
      if (kb_lo(j, z) < kb_hi(i, z) && kb_lo(i, z) < kb_hi(j, z)) { delta = i - j; break; }
    d |= (uint32_t)delta << (4 * t);
  }
  return d;
}
constexpr int kTotalKb = ph_first(5) + ph_n(5);
constexpr uint32_t kLastRelease = kTotalKb - 1 - 6;

static_assert(kTotalKb - kTailKb - 2 <= kLastRelease, "releases past the last reused slot");

template <int V> struct IC { static constexpr int v = V; };
template <int B, int E, class F> __device__ __forceinline__ void static_for(F&& f) {
  if constexpr (B < E) { f(IC<B>{}); static_for<B + 1, E>(f); }
}

template <int P, bool Z> struct Ph {
  static constexpr int start = ph_start(P, Z);
  static constexpr uint32_t deltas = ph_deltas(P, Z);
};

__device__ __align__(1024) uint8_t g_h[16 * kAtoms * 16384];
__device__ uint32_t g_flag[16 * 32];

__device__ __forceinline__ uint32_t smem_u32(const void* p) { return (uint32_t)__cvta_generic_to_shared(p); }
__device__ __forceinline__ void mbar_init(uint32_t bar, uint32_t cnt) {
  asm volatile("mbarrier.init.shared::cta.b64 [%0], %1;" ::"r"(bar), "r"(cnt) : "memory");
}
__device__ __forceinline__ void mbar_expect_tx(uint32_t bar, uint32_t bytes) {
  asm volatile("mbarrier.arrive.expect_tx.shared::cta.b64 _, [%0], %1;" ::"r"(bar), "r"(bytes) : "memory");
}
__device__ __forceinline__ void mbar_arrive(uint32_t bar) {
  asm volatile("mbarrier.arrive.shared::cta.b64 _, [%0];" ::"r"(bar) : "memory");
}
__device__ __forceinline__ void mbar_arrive_remote(uint32_t cluster_addr) {
  asm volatile("mbarrier.arrive.shared::cluster.b64 _, [%0];" ::"r"(cluster_addr) : "memory");
}
__device__ __forceinline__ uint32_t mapa(uint32_t addr, uint32_t cta) {
  uint32_t r;
  asm("mapa.shared::cluster.u32 %0, %1, %2;" : "=r"(r) : "r"(addr), "r"(cta));
  return r;
}
__device__ __forceinline__ void mbar_wait(uint32_t bar, uint32_t parity) {
  asm volatile(
      "{\n.reg .pred p;\n.reg .u32 n;\nmov.u32 n, 0;\n"
      "WAIT_LOOP:\n"
      "mbarrier.try_wait.parity.shared::cta.b64 p, [%0], %1;\n"
      "@p bra WAIT_DONE;\n"
      "add.u32 n, n, 1;\n"
      "setp.lt.u32 p, n, 4194304;\n"
      "@p bra WAIT_LOOP;\n"
      "trap;\n"
      "WAIT_DONE:\n}"
      ::"r"(bar), "r"(parity) : "memory");
}
__device__ __forceinline__ void mbar_wait_n(uint32_t bar, uint32_t parity, uint32_t& n) {
  asm volatile(
      "{\n.reg .pred p;\n"
      "WAIT_LOOP:\n"
      "mbarrier.try_wait.parity.shared::cta.b64 p, [%1], %2;\n"
      "@p bra WAIT_DONE;\n"
      "add.u32 %0, %0, 1;\n"
      "setp.lt.u32 p, %0, 4194304;\n"
      "@p bra WAIT_LOOP;\n"
      "trap;\n"
      "WAIT_DONE:\n}"
      : "+r"(n) : "r"(bar), "r"(parity) : "memory");
}
__device__ __forceinline__ void tma2d(uint32_t dst, const CUtensorMap* m, uint32_t bar, int c0, int c1) {
  asm volatile("cp.async.bulk.tensor.2d.shared::cluster.global.mbarrier::complete_tx::bytes [%0], [%1, {%3, %4}], [%2];"
               ::"r"(dst), "l"(m), "r"(bar), "r"(c0), "r"(c1) : "memory");
}
__device__ __forceinline__ void tma2d_mc(uint32_t dst, const CUtensorMap* m, uint32_t bar, int c0, int c1) {
  asm volatile("cp.async.bulk.tensor.2d.shared::cluster.global.mbarrier::complete_tx::bytes.multicast::cluster"
               " [%0], [%1, {%3, %4}], [%2], %5;"
               ::"r"(dst), "l"(m), "r"(bar), "r"(c0), "r"(c1), "h"((uint16_t)3) : "memory");
}
__device__ __forceinline__ void bulk_load(uint32_t dst, const void* src, uint32_t bytes, uint32_t bar) {
  asm volatile("cp.async.bulk.shared::cluster.global.mbarrier::complete_tx::bytes [%0], [%1], %2, [%3];"
               ::"r"(dst), "l"(src), "r"(bytes), "r"(bar) : "memory");
}
__device__ __forceinline__ void bulk_store(void* dst, uint32_t src, uint32_t bytes) {
  asm volatile("cp.async.bulk.global.shared::cta.bulk_group [%0], [%1], %2;" ::"l"(dst), "r"(src), "r"(bytes) : "memory");
}
__device__ __forceinline__ void tma2d_store(const CUtensorMap* m, uint32_t src, int c0, int c1) {
  asm volatile("cp.async.bulk.tensor.2d.global.shared::cta.bulk_group [%0, {%2, %3}], [%1];"
               ::"l"(m), "r"(src), "r"(c0), "r"(c1) : "memory");
}
__device__ __forceinline__ void tma3d_mc(uint32_t dst, const CUtensorMap* m, uint32_t bar, int c1, int c2) {
  asm volatile("cp.async.bulk.tensor.3d.shared::cluster.global.mbarrier::complete_tx::bytes.multicast::cluster"
               " [%0], [%1, {0, %3, %4}], [%2], %5;"
               ::"r"(dst), "l"(m), "r"(bar), "r"(c1), "r"(c2), "h"((uint16_t)3) : "memory");
}
__device__ __forceinline__ void pf2d(const CUtensorMap* m, int c0, int c1) {
  asm volatile("cp.async.bulk.prefetch.tensor.2d.L2.global [%0, {%1, %2}];" ::"l"(m), "r"(c0), "r"(c1) : "memory");
}
__device__ __forceinline__ void pf3d(const CUtensorMap* m, int c1, int c2) {
  asm volatile("cp.async.bulk.prefetch.tensor.3d.L2.global [%0, {0, %1, %2}];" ::"l"(m), "r"(c1), "r"(c2) : "memory");
}
__device__ __forceinline__ bool elect_one() {
  uint32_t p;
  asm volatile("{\n.reg .pred p;\nelect.sync _|p, 0xffffffff;\nselp.b32 %0, 1, 0, p;\n}" : "=r"(p));
  return p;
}
__device__ __forceinline__ void prefetch_map(const CUtensorMap* m) {
  asm volatile("prefetch.tensormap [%0];" ::"l"(m) : "memory");
}
__device__ __forceinline__ void spin_until(uint32_t t0, uint32_t d) {
  if (!d) return;
  uint32_t t;
  do { asm volatile("mov.u32 %0, %%clock;" : "=r"(t) :: "memory"); } while (t - t0 < d);
}
__device__ __forceinline__ void cp16(uint32_t dst, const void* src) {
  asm volatile("cp.async.cg.shared.global [%0], [%1], 16;" ::"r"(dst), "l"(src) : "memory");
}
__device__ __forceinline__ void cp_commit() { asm volatile("cp.async.commit_group;" ::: "memory"); }
template <int N> __device__ __forceinline__ void cp_wait() { asm volatile("cp.async.wait_group %0;" ::"n"(N) : "memory"); }
__device__ __forceinline__ void bulk_commit() { asm volatile("cp.async.bulk.commit_group;" ::: "memory"); }
__device__ __forceinline__ void bulk_wait_read() { asm volatile("cp.async.bulk.wait_group.read 0;" ::: "memory"); }
__device__ __forceinline__ void bulk_wait_all() { asm volatile("cp.async.bulk.wait_group 0;" ::: "memory"); }
__device__ __forceinline__ void fence_async_smem() { asm volatile("fence.proxy.async.shared::cta;" ::: "memory"); }
__device__ __forceinline__ void fence_async_global() { asm volatile("fence.proxy.async.global;" ::: "memory"); }
__device__ __forceinline__ void wg_fence() { asm volatile("wgmma.fence.sync.aligned;" ::: "memory"); }
__device__ __forceinline__ void wg_commit() { asm volatile("wgmma.commit_group.sync.aligned;" ::: "memory"); }
template <int N> __device__ __forceinline__ void wg_wait() {
  asm volatile("wgmma.wait_group.sync.aligned %0;" ::"n"(N) : "memory");
}
template <int N> __device__ __forceinline__ void pin(float (&d)[N]) {
#pragma unroll
  for (int i = 0; i < N; i++) asm volatile("" : "+f"(d[i])::"memory");
}
__device__ __forceinline__ uint64_t desc_a(uint32_t addr) {
  return (uint64_t)((addr >> 4) | (1u << 16)) | ((uint64_t)(64u | (1u << 30)) << 32);
}
__device__ __forceinline__ uint64_t desc_b(uint32_t addr) {
  return (uint64_t)((addr >> 4) | (512u << 16)) | ((uint64_t)(64u | (1u << 30)) << 32);
}
template <int Mode, int From, int To> __device__ __forceinline__ void desc_move(uint64_t& d) {
  if (Mode) asm volatile("{\n.reg .b32 l, h;\nmov.b64 {l, h}, %0;\nxor.b32 l, l, %1;\nmov.b64 %0, {l, h};\n}" : "+l"(d) : "n"(From ^ To));
  else asm volatile("{\n.reg .b32 l, h;\nmov.b64 {l, h}, %0;\nadd.s32 l, l, %1;\nmov.b64 %0, {l, h};\n}" : "+l"(d) : "n"(To - From));
}
__device__ __forceinline__ void desc_add(uint64_t& d, int step) {
  asm volatile("{\n.reg .b32 l, h;\nmov.b64 {l, h}, %0;\nadd.s32 l, l, %1;\nmov.b64 %0, {l, h};\n}" : "+l"(d) : "r"(step));
}
__device__ __forceinline__ void stsm4(uint32_t addr, uint32_t r0, uint32_t r1, uint32_t r2, uint32_t r3) {
  asm volatile("stmatrix.sync.aligned.m8n8.x4.shared.b16 [%0], {%1, %2, %3, %4};"
               ::"r"(addr), "r"(r0), "r"(r1), "r"(r2), "r"(r3) : "memory");
}
__device__ __forceinline__ void ldsm4(uint32_t (&r)[4], uint32_t addr) {
  asm volatile("ldmatrix.sync.aligned.m8n8.x4.shared.b16 {%0, %1, %2, %3}, [%4];"
               : "=r"(r[0]), "=r"(r[1]), "=r"(r[2]), "=r"(r[3]) : "r"(addr) : "memory");
}
__device__ __forceinline__ void stsm2(uint32_t addr, uint32_t r0, uint32_t r1) {
  asm volatile("stmatrix.sync.aligned.m8n8.x2.shared.b16 [%0], {%1, %2};" ::"r"(addr), "r"(r0), "r"(r1) : "memory");
}
__device__ __forceinline__ uint32_t pack_bf16(float lo, float hi) {
  uint32_t r;
  asm("cvt.rn.bf16x2.f32 %0, %1, %2;" : "=r"(r) : "f"(hi), "f"(lo));
  return r;
}
__device__ __forceinline__ float geglu(float g, float u) {
  float th;
  asm("tanh.approx.f32 %0, %1;" : "=f"(th) : "f"(g * fmaf(g * 0.0356774081363f, g, 0.7978845608029f)));
  const float p = (g * u) * 0.5f;
  return fmaf(p, th, p);
}

__device__ __forceinline__ void wgmma_n256(float (&d)[128], uint64_t da, uint64_t db, int scale_d) {
  asm volatile("{\n.reg .pred p;\nsetp.ne.b32 p, %130, 0;\n"
    "wgmma.mma_async.sync.aligned.m64n256k16.f32.bf16.bf16 "
    "{%0, %1, %2, %3, %4, %5, %6, %7, %8, %9, %10, %11, %12, %13, %14, %15, "
    "%16, %17, %18, %19, %20, %21, %22, %23, %24, %25, %26, %27, %28, %29, %30, %31, "
    "%32, %33, %34, %35, %36, %37, %38, %39, %40, %41, %42, %43, %44, %45, %46, %47, "
    "%48, %49, %50, %51, %52, %53, %54, %55, %56, %57, %58, %59, %60, %61, %62, %63, "
    "%64, %65, %66, %67, %68, %69, %70, %71, %72, %73, %74, %75, %76, %77, %78, %79, "
    "%80, %81, %82, %83, %84, %85, %86, %87, %88, %89, %90, %91, %92, %93, %94, %95, "
    "%96, %97, %98, %99, %100, %101, %102, %103, %104, %105, %106, %107, %108, %109, %110, %111, "
    "%112, %113, %114, %115, %116, %117, %118, %119, %120, %121, %122, %123, %124, %125, %126, %127}, "
    "%128, %129, p, 1, 1, 0, 1;\n}\n"
    : "+f"(d[0]), "+f"(d[1]), "+f"(d[2]), "+f"(d[3]), "+f"(d[4]), "+f"(d[5]), "+f"(d[6]), "+f"(d[7]),
      "+f"(d[8]), "+f"(d[9]), "+f"(d[10]), "+f"(d[11]), "+f"(d[12]), "+f"(d[13]), "+f"(d[14]), "+f"(d[15]),
      "+f"(d[16]), "+f"(d[17]), "+f"(d[18]), "+f"(d[19]), "+f"(d[20]), "+f"(d[21]), "+f"(d[22]), "+f"(d[23]),
      "+f"(d[24]), "+f"(d[25]), "+f"(d[26]), "+f"(d[27]), "+f"(d[28]), "+f"(d[29]), "+f"(d[30]), "+f"(d[31]),
      "+f"(d[32]), "+f"(d[33]), "+f"(d[34]), "+f"(d[35]), "+f"(d[36]), "+f"(d[37]), "+f"(d[38]), "+f"(d[39]),
      "+f"(d[40]), "+f"(d[41]), "+f"(d[42]), "+f"(d[43]), "+f"(d[44]), "+f"(d[45]), "+f"(d[46]), "+f"(d[47]),
      "+f"(d[48]), "+f"(d[49]), "+f"(d[50]), "+f"(d[51]), "+f"(d[52]), "+f"(d[53]), "+f"(d[54]), "+f"(d[55]),
      "+f"(d[56]), "+f"(d[57]), "+f"(d[58]), "+f"(d[59]), "+f"(d[60]), "+f"(d[61]), "+f"(d[62]), "+f"(d[63]),
      "+f"(d[64]), "+f"(d[65]), "+f"(d[66]), "+f"(d[67]), "+f"(d[68]), "+f"(d[69]), "+f"(d[70]), "+f"(d[71]),
      "+f"(d[72]), "+f"(d[73]), "+f"(d[74]), "+f"(d[75]), "+f"(d[76]), "+f"(d[77]), "+f"(d[78]), "+f"(d[79]),
      "+f"(d[80]), "+f"(d[81]), "+f"(d[82]), "+f"(d[83]), "+f"(d[84]), "+f"(d[85]), "+f"(d[86]), "+f"(d[87]),
      "+f"(d[88]), "+f"(d[89]), "+f"(d[90]), "+f"(d[91]), "+f"(d[92]), "+f"(d[93]), "+f"(d[94]), "+f"(d[95]),
      "+f"(d[96]), "+f"(d[97]), "+f"(d[98]), "+f"(d[99]), "+f"(d[100]), "+f"(d[101]), "+f"(d[102]), "+f"(d[103]),
      "+f"(d[104]), "+f"(d[105]), "+f"(d[106]), "+f"(d[107]), "+f"(d[108]), "+f"(d[109]), "+f"(d[110]), "+f"(d[111]),
      "+f"(d[112]), "+f"(d[113]), "+f"(d[114]), "+f"(d[115]), "+f"(d[116]), "+f"(d[117]), "+f"(d[118]), "+f"(d[119]),
      "+f"(d[120]), "+f"(d[121]), "+f"(d[122]), "+f"(d[123]), "+f"(d[124]), "+f"(d[125]), "+f"(d[126]), "+f"(d[127])
    : "l"(da), "l"(db), "r"(scale_d));
}

__device__ __forceinline__ void wgmma_n128(float (&d)[64], uint64_t da, uint64_t db, int scale_d) {
  asm volatile("{\n.reg .pred p;\nsetp.ne.b32 p, %66, 0;\n"
    "wgmma.mma_async.sync.aligned.m64n128k16.f32.bf16.bf16 "
    "{%0, %1, %2, %3, %4, %5, %6, %7, %8, %9, %10, %11, %12, %13, %14, %15, "
    "%16, %17, %18, %19, %20, %21, %22, %23, %24, %25, %26, %27, %28, %29, %30, %31, "
    "%32, %33, %34, %35, %36, %37, %38, %39, %40, %41, %42, %43, %44, %45, %46, %47, "
    "%48, %49, %50, %51, %52, %53, %54, %55, %56, %57, %58, %59, %60, %61, %62, %63}, "
    "%64, %65, p, 1, 1, 0, 1;\n}\n"
    : "+f"(d[0]), "+f"(d[1]), "+f"(d[2]), "+f"(d[3]), "+f"(d[4]), "+f"(d[5]), "+f"(d[6]), "+f"(d[7]),
      "+f"(d[8]), "+f"(d[9]), "+f"(d[10]), "+f"(d[11]), "+f"(d[12]), "+f"(d[13]), "+f"(d[14]), "+f"(d[15]),
      "+f"(d[16]), "+f"(d[17]), "+f"(d[18]), "+f"(d[19]), "+f"(d[20]), "+f"(d[21]), "+f"(d[22]), "+f"(d[23]),
      "+f"(d[24]), "+f"(d[25]), "+f"(d[26]), "+f"(d[27]), "+f"(d[28]), "+f"(d[29]), "+f"(d[30]), "+f"(d[31]),
      "+f"(d[32]), "+f"(d[33]), "+f"(d[34]), "+f"(d[35]), "+f"(d[36]), "+f"(d[37]), "+f"(d[38]), "+f"(d[39]),
      "+f"(d[40]), "+f"(d[41]), "+f"(d[42]), "+f"(d[43]), "+f"(d[44]), "+f"(d[45]), "+f"(d[46]), "+f"(d[47]),
      "+f"(d[48]), "+f"(d[49]), "+f"(d[50]), "+f"(d[51]), "+f"(d[52]), "+f"(d[53]), "+f"(d[54]), "+f"(d[55]),
      "+f"(d[56]), "+f"(d[57]), "+f"(d[58]), "+f"(d[59]), "+f"(d[60]), "+f"(d[61]), "+f"(d[62]), "+f"(d[63])
    : "l"(da), "l"(db), "r"(scale_d));
}

__device__ __forceinline__ void wgmma_n112(float (&d)[56], uint64_t da, uint64_t db, int scale_d) {
  asm volatile("{\n.reg .pred p;\nsetp.ne.b32 p, %58, 0;\n"
    "wgmma.mma_async.sync.aligned.m64n112k16.f32.bf16.bf16 "
    "{%0, %1, %2, %3, %4, %5, %6, %7, %8, %9, %10, %11, %12, %13, %14, %15, "
    "%16, %17, %18, %19, %20, %21, %22, %23, %24, %25, %26, %27, %28, %29, %30, %31, "
    "%32, %33, %34, %35, %36, %37, %38, %39, %40, %41, %42, %43, %44, %45, %46, %47, "
    "%48, %49, %50, %51, %52, %53, %54, %55}, "
    "%56, %57, p, 1, 1, 0, 1;\n}\n"
    : "+f"(d[0]), "+f"(d[1]), "+f"(d[2]), "+f"(d[3]), "+f"(d[4]), "+f"(d[5]), "+f"(d[6]), "+f"(d[7]),
      "+f"(d[8]), "+f"(d[9]), "+f"(d[10]), "+f"(d[11]), "+f"(d[12]), "+f"(d[13]), "+f"(d[14]), "+f"(d[15]),
      "+f"(d[16]), "+f"(d[17]), "+f"(d[18]), "+f"(d[19]), "+f"(d[20]), "+f"(d[21]), "+f"(d[22]), "+f"(d[23]),
      "+f"(d[24]), "+f"(d[25]), "+f"(d[26]), "+f"(d[27]), "+f"(d[28]), "+f"(d[29]), "+f"(d[30]), "+f"(d[31]),
      "+f"(d[32]), "+f"(d[33]), "+f"(d[34]), "+f"(d[35]), "+f"(d[36]), "+f"(d[37]), "+f"(d[38]), "+f"(d[39]),
      "+f"(d[40]), "+f"(d[41]), "+f"(d[42]), "+f"(d[43]), "+f"(d[44]), "+f"(d[45]), "+f"(d[46]), "+f"(d[47]),
      "+f"(d[48]), "+f"(d[49]), "+f"(d[50]), "+f"(d[51]), "+f"(d[52]), "+f"(d[53]), "+f"(d[54]), "+f"(d[55])
    : "l"(da), "l"(db), "r"(scale_d));
}

__device__ __forceinline__ void wgmma_rs_n64(float (&d)[32], const uint32_t (&a)[4], uint64_t db, int scale_d) {
  asm volatile("{\n.reg .pred p;\nsetp.ne.b32 p, %37, 0;\n"
    "wgmma.mma_async.sync.aligned.m64n64k16.f32.bf16.bf16 "
    "{%0, %1, %2, %3, %4, %5, %6, %7, %8, %9, %10, %11, %12, %13, %14, %15, "
    "%16, %17, %18, %19, %20, %21, %22, %23, %24, %25, %26, %27, %28, %29, %30, %31}, "
    "{%32, %33, %34, %35}, %36, p, 1, 1, 1;\n}\n"
    : "+f"(d[0]), "+f"(d[1]), "+f"(d[2]), "+f"(d[3]), "+f"(d[4]), "+f"(d[5]), "+f"(d[6]), "+f"(d[7]),
      "+f"(d[8]), "+f"(d[9]), "+f"(d[10]), "+f"(d[11]), "+f"(d[12]), "+f"(d[13]), "+f"(d[14]), "+f"(d[15]),
      "+f"(d[16]), "+f"(d[17]), "+f"(d[18]), "+f"(d[19]), "+f"(d[20]), "+f"(d[21]), "+f"(d[22]), "+f"(d[23]),
      "+f"(d[24]), "+f"(d[25]), "+f"(d[26]), "+f"(d[27]), "+f"(d[28]), "+f"(d[29]), "+f"(d[30]), "+f"(d[31])
    : "r"(a[0]), "r"(a[1]), "r"(a[2]), "r"(a[3]), "l"(db), "r"(scale_d));
}

template <int N>
__device__ __forceinline__ void epi_step(float (&d)[N], int s, uint32_t stg_lane) {
  constexpr int U = N / 2;
  const int j = 8 * s;
  uint32_t r0 = pack_bf16(geglu(d[j + 0], d[j + 0 + U]), geglu(d[j + 1], d[j + 1 + U]));
  uint32_t r1 = pack_bf16(geglu(d[j + 2], d[j + 2 + U]), geglu(d[j + 3], d[j + 3 + U]));
  uint32_t r2 = pack_bf16(geglu(d[j + 4], d[j + 4 + U]), geglu(d[j + 5], d[j + 5 + U]));
  uint32_t r3 = pack_bf16(geglu(d[j + 6], d[j + 6 + U]), geglu(d[j + 7], d[j + 7 + U]));
  stsm4((stg_lane ^ ((s & 3) << 5)) + (s >> 2) * 16384, r0, r1, r2, r3);
}

__device__ __forceinline__ void epi_half_step(const float* g, const float* u, int s, uint32_t stg_lane2) {
  const int j = 4 * s;
  uint32_t r0 = pack_bf16(geglu(g[j + 0], u[j + 0]), geglu(g[j + 1], u[j + 1]));
  uint32_t r1 = pack_bf16(geglu(g[j + 2], u[j + 2]), geglu(g[j + 3], u[j + 3]));
  stsm2((stg_lane2 ^ ((s & 7) << 4)) + (s >> 3) * 16384, r0, r1);
}

struct Maps { CUtensorMap x, g, u, g1, u1, d, d1, o, g48, u48, d48, d16, hl, hs; };

template <bool X>
__global__ void __cluster_dims__(2, 1, 1) __launch_bounds__(384, 1)
geglu_ffn_kernel(const uint8_t* __restrict__ px, const uint8_t* __restrict__ pg, const uint8_t* __restrict__ pu,
                 uint8_t* p_h, uint32_t* p_flag,
                 const __grid_constant__ Maps tm) {
  extern __shared__ __align__(1024) uint8_t smem_raw[];
  const uint32_t base = mapa(smem_u32(smem_raw), blockIdx.x & 1);
  const uint32_t stg = base + kRing;
  const uint32_t bar_full = stg + kStg, bar_empty = bar_full + 64;
  const uint32_t bar_stg_free = bar_empty + 64, bar_ready = bar_stg_free + 16;
  const int tid = threadIdx.x;
  const uint32_t rank = blockIdx.x & 1;
  const bool ex = X && blockIdx.x >= 128;
  const int p4 = ((blockIdx.x >> 1) - 4) & 63;
  int idx;
  asm("{\n.reg .pred p, q;\n.reg .s32 a, b;\nsetp.lt.s32 p, %1, 32;\nsetp.lt.s32 q, %1, 60;\n"
      "mad.lo.s32 a, %1, 293, -928;\nshr.s32 a, a, 8;\nmad.lo.s32 b, %1, 8, -448;\n"
      "selp.s32 b, %1, b, p;\nxor.pred p, p, q;\nselp.s32 %0, a, b, p;\n}" : "=r"(idx) : "r"(p4));
  const int mi = ex ? (blockIdx.x & 2) * 2 : idx & 7, g = ex ? 27 : idx >> 3;
  const int m = 2 * mi + rank;

  uint32_t t_entry = 0;
  if (tid < 256) {
    const int r = tid >> 4, c = tid & 15;
    const uint32_t wd = base + 16384 + (c >> 3) * 8192 + r * 128 + (((c ^ r) & 7) << 4);
    const uint32_t wo = r * (kF * 2) + g * 256 + c * 16;
    const uint32_t xd = (X ? stg : base) + tid * 16;
    const uint8_t* xs = px + (m * 128 + (tid >> 3)) * (kD * 2) + (((tid ^ (tid >> 3)) & 7) << 4);
    cp16(wd, pg + wo);
    cp16(wd + 16384, pu + wo);
#pragma unroll
    for (int i = 0; i < 4; i++) cp16(xd + i * 4096, xs + i * 32 * (kD * 2));
    cp_commit();
    asm volatile("barrier.cluster.arrive.relaxed.aligned;" ::: "memory");
#pragma unroll
    for (int j = 1; j < 4; j++) {
      cp16(wd + j * 2048, pg + wo + j * 16 * (kF * 2));
      cp16(wd + 16384 + j * 2048, pu + wo + j * 16 * (kF * 2));
      cp_commit();
    }
  }
  const int warp = __shfl_sync(0xffffffff, tid >> 5, 0), wg = warp >> 2;
  if (wg == 2) {
    asm volatile("mov.u32 %0, %%clock;" : "=r"(t_entry) :: "memory");
    if (warp == 8) {
      if (elect_one()) {
        prefetch_map(rank ? &tm.u : &tm.g);
        prefetch_map(&tm.x);
#pragma unroll
        for (int s = 0; s < 8; s++) mbar_init(bar_full + 8 * s, 1);
        mbar_arrive(bar_full);
        asm volatile("fence.mbarrier_init.release.cluster;" ::: "memory");
        fence_async_smem();
      }
    } else if (warp == 9) {
      if (elect_one()) {
#pragma unroll
        for (int s = 0; s < 8; s++) mbar_init(bar_empty + 8 * s, 4);
        asm volatile("fence.mbarrier_init.release.cluster;" ::: "memory");
      }
    } else if (warp == 10) {
      if (elect_one()) {
#pragma unroll
        for (int s = 0; s < 9; s++) mbar_init(bar_stg_free + 8 * s, 1);
        asm volatile("fence.mbarrier_init.release.cluster;" ::: "memory");
      }
    }
  }
  __syncwarp();
  if (wg == 2) asm volatile("barrier.cluster.arrive.relaxed.aligned;" ::: "memory");

  if (wg == 2) {
    asm volatile("setmaxnreg.dec.sync.aligned.u32 40;");
    asm volatile("barrier.cluster.wait.aligned;" ::: "memory");
    if (warp == 9) {
      auto staged = [&](int buf) {
        asm volatile("{\n.reg .pred p;\nsetp.ne.u32 p, %0, 0;\n@p bar.sync 4, 288;\n@!p bar.sync 3, 288;\n}" ::"r"(buf) : "memory");
      };
      if (ex) {
        const int lane = tid & 31, ch = lane & 7, r0 = lane >> 3;
        if (lane == 0) prefetch_map(rank ? &tm.u1 : &tm.g1);
#pragma unroll 1
        for (int c = 0; c < 8; c++) {
          const int buf = (0x92 >> c) & 1, half = (0xb2 >> c) & 1, mt = m + ((0x66244200 >> (4 * c)) & 15);
          uint8_t* dst = p_h + (size_t)(mt * kAtoms + 41 + 8 * half + (ch & 6)) * 16384 + r0 * 128 + 96 + (ch & 1) * 16;
          const uint32_t src = stg + buf * 16384 + r0 * 128 + ((ch ^ r0) << 4);
          staged(buf);
#pragma unroll 1
          for (int q = 0; q < 16384; q += 2048) {
            uint4 v[4];
#pragma unroll
            for (int j = 0; j < 4; j++)
              asm volatile("ld.shared.v4.u32 {%0, %1, %2, %3}, [%4];" : "=r"(v[j].x), "=r"(v[j].y), "=r"(v[j].z), "=r"(v[j].w)
                           : "r"((src ^ ((j & 1) << 6)) + q + j * 512) : "memory");
#pragma unroll
            for (int j = 0; j < 4; j++) *(uint4*)(dst + q + j * 512) = v[j];
          }
          __syncwarp();
          if (lane == 0) {
            mbar_arrive(bar_stg_free + 8 * buf);
            if (half) asm volatile("red.release.gpu.global.add.u32 [%0], 8;" ::"l"(p_flag + mt * 32 + 7) : "memory");
          }
        }
        return;
      }
      if (!elect_one()) return;
      prefetch_map(rank ? &tm.u1 : &tm.g1);
      auto late_maps = [&]() {
        if (X) {
          prefetch_map(rank ? &tm.u48 : &tm.g48);
          prefetch_map(&tm.d48);
          prefetch_map(&tm.d16);
          prefetch_map(&tm.hs);
          prefetch_map(&tm.hl);
        }
      };
      auto mid_maps = [&]() {
        prefetch_map(&tm.d);
        prefetch_map(&tm.d1);
        prefetch_map(&tm.o);
      };
      uint8_t* hdst = p_h + (size_t)m * kAtoms * 16384;
      uint32_t* flag = p_flag + m * 32;
#pragma unroll 1
      for (int c = 0; c < (X ? 6 : 7); c++) {
        const int buf = (0x52 >> c) & 1;
        const int atom = c == 2 ? 16 + g : (c < 2 ? 0 : c < 5 ? 24 : 40) + 2 * g + buf;
        staged(buf);
#pragma unroll 1
        for (int q = 0; q < 4; q++) {
          if (q) __nanosleep(kStoreGap);
          bulk_store(hdst + (size_t)atom * 16384 + q * 4096, stg + buf * 16384 + q * 4096, 4096);
          bulk_commit();
          bulk_wait_read();
        }
        mbar_arrive(bar_stg_free + 8 * buf);
        if (c == 0) mid_maps();
        if (c == 2) late_maps();
        if (!((0x72 >> c) & 1)) continue;
        bulk_wait_all();
        asm volatile("red.release.gpu.global.add.u32 [%0], 1;" ::"l"(flag + c) : "memory");
        asm volatile("{\n.reg .pred p;\nsetp.ne.u32 p, %0, 0;\n@p bar.arrive 5, 64;\n@!p bar.arrive 6, 64;\n}" ::"r"(c & 1) : "memory");
      }
    } else if (warp == 10 || (X && warp == 11)) {
      if (ex || !elect_one()) return;
      const uint32_t* flag = p_flag + m * 32;
      uint32_t epoch;
      asm volatile("ld.relaxed.gpu.global.u32 %0, [%1];" : "=r"(epoch) : "l"(flag + 6) : "memory");
      epoch &= ~7u;
      auto poll = [&](int c) {
        uint32_t v, n = 0;
        while (true) {
          asm volatile("ld.acquire.gpu.global.u32 %0, [%1];" : "=r"(v) : "l"(flag + c) : "memory");
          if ((int32_t)(v - epoch) >= 8) break;
          if (++n > (1u << 20)) __trap();
          __nanosleep(kPollGap);
        }
      };
      if (X && warp == 11) {
        asm volatile("bar.sync 7, 288;" ::: "memory");
#pragma unroll 1
        for (int q = 0; q < 4; q++) {
          if (q) __nanosleep(kStoreGap);
          tma2d_store(&tm.hs, stg + 16384 + q * 4096, 0, (m * kAtoms + 41 + 2 * g) * 128 + q * 32);
          bulk_commit();
          bulk_wait_read();
        }
        mbar_arrive(bar_stg_free + 8);
        bulk_wait_all();
        asm volatile("red.release.gpu.global.add.u32 [%0], 1;" ::"l"(flag + 6) : "memory");
        asm volatile("bar.arrive 6, 64;" ::: "memory");
        return;
      }
#pragma unroll 1
      for (int c = 1; c < 7; c += c == 1 ? 3 : 1) {
        if (X && c == 6) poll(7);
        asm volatile("{\n.reg .pred p;\nsetp.ne.u32 p, %0, 0;\n@p bar.sync 5, 64;\n@!p bar.sync 6, 64;\n}" ::"r"(c & 1) : "memory");
        poll(c);
        fence_async_global();
        mbar_arrive(bar_ready + 8 * c);
      }
    } else if (warp == 8) {
      if (!elect_one()) return;
      uint32_t it = 4, off;
      auto acquire_slot = [&](uint32_t deltas, int stages, int t, uint32_t bytes) {
        uint32_t d = t < stages ? (deltas >> (4 * t)) & 15u : (uint32_t)stages;
        if (d) { uint32_t j = it - d; mbar_wait(bar_empty + 8 * (j & 7), (j >> 3) & 1); }
        uint32_t fb = bar_full + 8 * (it & 7);
        mbar_expect_tx(fb, bytes);
        it++;
        return fb;
      };
#pragma unroll
      for (int t = 1; t <= 3; t++) {
        spin_until(t_entry, t == 1 ? 900 : t == 2 ? 1700 : 2500);
        mbar_expect_tx(bar_full + 8 * t, kBig);
        tma3d_mc(base + t * kBig + 16384 + rank * 16384, rank ? &tm.u : &tm.g, bar_full + 8 * t, t * 64, 2 * g);
        tma2d(X && t == 1 && !ex ? stg + 16384 : base + t * kBig, &tm.x, bar_full + 8 * t, t * 64, m * 128);
      }
      const CUtensorMap* tm_w = rank ? &tm.u : &tm.g;
      const CUtensorMap* tm_w1 = rank ? &tm.u1 : &tm.g1;
      const uint8_t* hsrc = p_h + (size_t)m * kAtoms * 16384;
      auto big_phase = [&](auto ic, int start, uint32_t deltas, int t0, int mt, int atom, auto&& prefetch) {
        constexpr int mode = decltype(ic)::v;
        off = mode == 1 ? 8 * 16384 : start * kBig;
#pragma unroll 1
        for (int t = t0; t < 16; t++) {
          const bool keep = mode == 2 && t < 4;
          const int k = mode == 2 ? (t * 64 + 768) & 1023 : t * 64;
          uint32_t fb = acquire_slot(deltas, 4, t, mode == 1 ? kBig - 4096 : keep ? kBig - 16384 : kBig);
          uint32_t sa = base + off, sb = sa + 16384 + rank * 16384;
          if (!keep) tma2d(sa, &tm.x, fb, k, mt * 128);
          if (mode == 1) {
            if (off == kRing - 16384) sb -= kRing;
            tma2d_mc(sb, tm_w1, fb, kT2 + 64 * g, k);
            tma2d_mc(sb + 8192, rank ? &tm.u48 : &tm.g48, fb, kT2 + 512 + 48 * g, k);
          } else {
            tma3d_mc(sb, tm_w, fb, k, atom);
          }
          prefetch(t);
          off += kBig;
          if (off >= kRing) off -= kRing;
        }
      };
      auto half_phase = [&](int start, uint32_t deltas, int mt, int atom) {
        off = start * kSmall;
#pragma unroll 1
        for (int t = 0; t < 16; t++) {
          uint32_t fb = acquire_slot(deltas, 6, t, kSmall);
          uint32_t sa = base + off;
          tma2d(sa, &tm.x, fb, t * 64, mt * 128);
          tma2d_mc(sa + 16384 + rank * 8192, tm_w1, fb, atom * 64, t * 64);
          off += kSmall;
          if (off == kRing) off = 0;
        }
      };
      auto g2_run = [&](uint32_t deltas, int t0, int cls, int atom, int step, int n) {
        mbar_wait(bar_ready + 8 * cls, 0);
#pragma unroll 1
        for (int t = 0; t < n; t++, atom += step) {
          uint32_t fb = acquire_slot(deltas, 6, t0 + t, kSmall);
          uint32_t sa = base + off;
          const uint32_t sb = sa + 16384 + rank * 8192;
          const int col = g * 128 + rank * 64;
          if (X && cls == 6) {
            tma2d(sa, &tm.hl, fb, 0, (m * kAtoms + atom) * 128);
            tma2d_mc(sb, &tm.d48, fb, col, kT2 + 512 + 48 * t);
            tma2d_mc(sb + 6144, &tm.d16, fb, col, kXCol + 16 * t);
          } else {
            bulk_load(sa, hsrc + (size_t)atom * 16384, 16384, fb);
            tma2d_mc(sb, &tm.d1, fb, col, X && cls == 5 ? kT2 + 64 * t : atom * 64);
          }
          off += kSmall;
          if (off == kRing) off = 0;
        }
      };
      if (ex) {
#pragma unroll 1
        for (int r = 0; r < 3; r++) {
          big_phase(IC<0>{}, r == 0 ? 0 : r == 1 ? Ph<2, false>::start : Ph<4, false>::start,
                    r == 1 ? Ph<2, false>::deltas : Ph<4, false>::deltas, r ? 0 : 4, r ? m + 2 + 2 * r : m, 54, [](int) {});
          if (r < 2) half_phase(r ? Ph<3, false>::start : Ph<1, false>::start, r ? Ph<3, false>::deltas : Ph<1, false>::deltas, m + 2, 54 + r);
        }
#pragma unroll 1
        for (int j = 4; j < 7; j++) mbar_wait(bar_empty + 8 * j, 1);
        return;
      }
      if (X) {
#pragma unroll 1
        for (int i = 4; i < 32; i++) {
          const int k = blk_k(i) * 64, units = blk_units(i);
          const uint32_t sb = base + blk_b(i) * 16384;
          uint32_t fb = acquire_slot(i < 16 ? 0x65544466 : i < 24 ? 0x44444466 : 0x54656454, 8, i & 7, units * 16384);
          if (units > 1) tma2d(base + blk_a(i) * 16384, &tm.x, fb, k, m * 128);
          if (units < 3) tma2d_mc(sb + rank * 8192, tm_w1, fb, (16 + g) * 64, k);
          else tma3d_mc(sb + rank * 16384, tm_w, fb, k, 2 * g);
          if (i == 19) pf2d(tm_w1, (16 + g) * 64, (8 + mi) * 64);
          if (i == 9) pf3d(tm_w, ((12 + mi) & 15) * 64, 24 + 2 * g);
          if (i == 17) pf3d(tm_w, (4 + mi) * 64, 24 + 2 * g);
        }
      } else {
        big_phase(IC<0>{}, 0, 0, 4, m, 2 * g, [&](int t) {
          if (t == 4) pf2d(tm_w1, (16 + g) * 64, mi * 64);
          if (t == 6) pf2d(tm_w1, (16 + g) * 64, (8 + mi) * 64);
          if (t == 10) pf3d(tm_w, mi * 64, 24 + 2 * g);
          if (t == 13) pf3d(tm_w, (8 + mi) * 64, 24 + 2 * g);
        });
        half_phase(Ph<1, false>::start, Ph<1, false>::deltas, m, 16 + g);
      }
      big_phase(IC<X ? 2 : 0>{}, Ph<2, X>::start, Ph<2, X>::deltas, 0, m, 24 + 2 * g, [&](int t) {
        if (t == 4) pf3d(&tm.d, m * 64, g * 2);
        if (t == 8) pf3d(tm_w, mi * 64, 40 + 2 * g);
        if (t == 12) pf3d(tm_w, (8 + mi) * 64, 40 + 2 * g);
      });
      off = Ph<3, X>::start * kSmall;
      g2_run(Ph<3, X>::deltas, 0, 1, 0, 1, kG2a);
      big_phase(IC<X ? 1 : 0>{}, Ph<4, X>::start, Ph<4, X>::deltas, 0, m, 40 + 2 * g, [&](int t) {
        if (t == 4) pf3d(&tm.d, (16 + m) * 64, g * 2);
        if (t == 8) pf3d(&tm.d, (32 + m) * 64, g * 2);
        if (t == 12 && m < 8) pf3d(&tm.d, (48 + m) * 64, g * 2);
      });
      off = Ph<5, X>::start * kSmall;
      g2_run(Ph<5, X>::deltas, 0, 4, kG2a, 1, 40 - kG2a);
      g2_run(0, 6, 5, 40, 2, 8);
      g2_run(0, 6, 6, 41, 2, 8);
    }
  } else {
    asm volatile("setmaxnreg.inc.sync.aligned.u32 232;");
    const int lane = tid & 31;
    const uint32_t stg_row = warp * 16 + (lane & 15);
    const uint32_t stg_lane2 = __shfl_sync(0xffffffff, stg + stg_row * 128 + ((lane & 7) << 4), lane);
    const uint32_t stg_lane = stg_lane2 ^ (lane & 16);
    const uint32_t rel_addr = mapa(bar_empty, tid & 1);
    const bool releaser = (tid & 127) < 2;
    const uint32_t a_base = (base & 0x3FFFF) + (X ? kRing : 0) + wg * 8192, b_base = (base & 0x3FFFF) + 16384;
    const bool always = blockIdx.x != 0x7ffffff0;
    float A[128], B[64], G[56], U[56];
#pragma unroll
    for (int i = 0; i < 128; i++) {
      if (X) asm volatile("" : "=f"(A[i]));
      else A[i] = 0.f;
    }
#pragma unroll
    for (int i = 0; i < 64; i++) B[i] = 0.f;
    uint32_t retries = 0;
    uint64_t da = __shfl_sync(0xffffffff, desc_a(a_base) + ((uint64_t)lane << 32), 0);
    uint64_t db = __shfl_sync(0xffffffff, desc_b(b_base) + ((uint64_t)lane << 33), 0);

    auto kb = [&](auto ic, int acc, int step, bool release = true, uint32_t flip = 0) {
      constexpr int i = decltype(ic)::v, p = i < 32 ? blk_units(i) < 3 : kb_phase(i);
      constexpr int o = kb_lo(i, X) * 1024, op = kb_lo(i - 1, X) * 1024;
      mbar_wait_n(bar_full + 8 * (i & 7), ((i >> 3) & 1) ^ flip, retries);
      if (i < 32) {
        desc_move<i & 1, blk_a(i - 1) * 1024, blk_a(i) * 1024>(da);
        desc_move<i & 1, blk_b(i - 1) * 1024, blk_b(i) * 1024>(db);
      } else if (i < 64 || (X && i >= 104 && i < 112)) {
        desc_add(da, step);
        desc_add(db, step);
      } else {
        desc_move<i & 1, op, o>(da);
        desc_move<i & 1, (op + 1024) % 12288, (o + 1024) % 12288>(db);
      }
      wg_fence();
#pragma unroll
      for (int q = 0; q < 4; q++) {
        if constexpr (p & 1) {
          wgmma_n128(B, da + 2 * q, db + 128 * q, acc || q);
        } else if constexpr (p == 4) {
          wgmma_n112(G, da + 2 * q, db + 128 * q, acc || q);
          wgmma_n112(U, da + 2 * q, db + 1024 + 128 * q, acc || q);
        } else {
          wgmma_n256(A, da + 2 * q, db + 128 * q, acc || q);
        }
      }
      wg_commit();
      wg_wait<1>();
      if (release && releaser) mbar_arrive_remote(rel_addr + 8 * ((i - 1) & 7));
    };
    auto stg_publish = [&](int buf) {
      fence_async_smem();
      if (buf == 2) asm volatile("bar.arrive 7, 288;" ::: "memory");
      else if (buf) asm volatile("bar.arrive 4, 288;" ::: "memory");
      else asm volatile("bar.arrive 3, 288;" ::: "memory");
    };

    {
      auto slice_ready = [&]() {
        fence_async_smem();
        asm volatile("bar.sync 1, 256;" ::: "memory");
      };
      pin(B);
      asm volatile("barrier.cluster.wait.aligned;" ::: "memory");
      cp_wait<3>();
      slice_ready();
      wg_fence();
      wgmma_n256(A, da, db, 0);
      cp_wait<2>();
      slice_ready();
      wgmma_n256(A, da + 2, db + 128, 1);
      cp_wait<1>();
      slice_ready();
      wgmma_n256(A, da + 4, db + 256, 1);
      cp_wait<0>();
      slice_ready();
      wgmma_n256(A, da + 6, db + 384, 1);
      wg_commit();
      wg_wait<1>();
    }

    if constexpr (X) {
      uint32_t held[8] = {};
      if (!ex) static_for<1, 32>([&](auto ic) {
        constexpr int i = decltype(ic)::v;
        kb(ic, 1, 0);
        if constexpr (i >= 24) {
          if (i == 24) pin(A);
          constexpr int s0 = i - 24 + (i > 24), s1 = i < 31 ? i - 23 : 7;
          if (i == 27) stg_publish(0);
          if (always) {
#pragma unroll
            for (int s = 0; s < (i == 25 ? s0 : 0); s++)
              stsm4(stg_lane ^ (s << 5), held[4 * s], held[4 * s + 1], held[4 * s + 2], held[4 * s + 3]);
#pragma unroll
            for (int s = s0; s <= s1; s++) {
              if (i > 24) {
                epi_step(A, s, stg_lane);
              } else {
#pragma unroll
                for (int j = 4 * s; j < 4 * s + 4; j++)
                  held[j] = pack_bf16(geglu(A[2 * j], A[2 * j + 64]), geglu(A[2 * j + 1], A[2 * j + 65]));
              }
            }
          }
          if (i == 31) stg_publish(1);
        }
      });
      desc_add(da, (ex ? -blk_a(0) : -blk_a(31)) * 1024);
      desc_add(db, ex ? 0 : (1 - blk_b(31)) * 1024);
    }
    int r = X && !ex;
    uint32_t h = 0;
    auto ring_step = [&](auto ic) {
      constexpr int i = decltype(ic)::v;
      constexpr int s0 = i == 32 ? 0 : kb_lo(i - 32, false) - kb_lo(i - 33, false), s1 = kb_lo(i, false) - kb_lo(i - 1, false);
      constexpr int s2 = X && i >= 48 ? s1 : kb_lo(i + 32, false) - kb_lo(i + 31, false);
      const int pat = X && !ex ? 0 : r;
      return s0 == s1 && s1 == s2 ? s0 * 1024 : pat == 0 ? s0 * 1024 : pat == 1 ? s1 * 1024 : s2 * 1024;
    };
    auto step = [&](auto ic) {
      constexpr int i = decltype(ic)::v, p = kb_phase(i), t = i & 15;
      if constexpr (X && p == 2) {
        if (t || r || h) kb(ic, t || h, t || !h ? ring_step(ic) : ring_step(IC<40>{}), true, h);
      } else if constexpr (X && p == 3) {
        if (r != 2) kb(ic, t, ring_step(ic));
        else if (t == 0) wg_wait<0>();
      } else {
        if (i != 32 || r) kb(ic, t || (!X && p == 3 && r == 2), ring_step(ic));
      }
      if constexpr (p == 2 && t >= kHalfEpi && t < kHalfEpi + 4) {
        if (X ? r != 0 && !h : r == 1) {
          if (t == kHalfEpi) { pin(B); mbar_wait_n(bar_stg_free, 0, retries); }
          epi_step(B, t - kHalfEpi, stg_lane);
          if (t == kHalfEpi + 3) stg_publish(0);
        }
      }
      if constexpr (p == 3) {
        if (t == 0) pin(A);
        if (t == 0 && r != 0) mbar_wait_n(bar_stg_free, X ? 1 : r & 1, retries);
        if (t == 8 && r != 0) mbar_wait_n(bar_stg_free + 8, (r - 1) & 1, retries);
        if (always) epi_half_step(A, A + 64, t, stg_lane2);
        if (t == 7 || t == 15) stg_publish(t == 15);
      }
    };
    const int rounds = X && !ex ? 2 : 3;
#pragma unroll 1
    for (; r < rounds; r++) {
      if constexpr (X) {
#pragma unroll 1
        for (h = 0; h < 2; h++) static_for<32, 40>(step);
      } else {
        static_for<32, 48>(step);
      }
      static_for<48, 64>(step);
    }
    if (X && ex) return;
    if constexpr (X) {
#pragma unroll
      for (int i = 0; i < 56; i++) {
        asm volatile("" : "=f"(G[i]), "=f"(U[i]));
      }
      {
        desc_move<0, kb_lo(63, X) * 1024, kb_lo(71, X) * 1024>(da);
        desc_move<0, kb_lo(63, X) * 1024, kb_lo(71, X) * 1024>(db);
#pragma unroll 1
        for (uint32_t h = 1; h < 2; h--) {
          static_for<72, 80>([&](auto ic) {
            kb(ic, decltype(ic)::v != 72 || !h, 0, true, h);
          });
        }
      }
      static_for<80, 96>([&](auto ic) {
        constexpr int i = decltype(ic)::v, t = i - 80;
        kb(ic, i != 64, 0);
        if constexpr (t >= 0 && t < 14) {
          if (t == 0) { pin(G); pin(U); mbar_wait_n(bar_stg_free, 0, retries); }
          if (t == 8) mbar_wait_n(bar_stg_free + 8, 1, retries);
          if (always) epi_half_step(G, U, t, stg_lane2);
          if (t == 7 || t == 13) stg_publish(t == 13 ? 2 : 0);
        }
      });
    }
    if constexpr (X) {
#pragma unroll 1
      for (uint32_t h = 1; h < 2; h--) {
        static_for<104, 112>([&](auto ic) {
          constexpr int i = decltype(ic)::v, s0 = kb_lo(i, X) - kb_lo(i - 1, X), s1 = kb_lo(i - 8, X) - kb_lo(i - 9, X);
          kb(ic, 1, (h ? s1 : s0) * 1024, true, h);
        });
      }
    }
    static_for<X ? 112 : 96, kTotalKb - kTailKb>([&](auto ic) { kb(ic, 1, 0); });
    mbar_wait_n(bar_stg_free, 1, retries);
    mbar_wait_n(bar_stg_free + 8, 0, retries);
    auto out_half = [&](int a, const float* v) {
#pragma unroll
      for (int s = 0; s < 4; s++) {
        const int j = s * 8;
        stsm4((stg_lane ^ (s << 5)) + a * 16384, pack_bf16(v[j], v[j + 1]), pack_bf16(v[j + 2], v[j + 3]),
              pack_bf16(v[j + 4], v[j + 5]), pack_bf16(v[j + 6], v[j + 7]));
      }
      fence_async_smem();
      __syncwarp();
      if (lane == 0) tma2d_store(&tm.o, stg + a * 16384 + warp * 2048, g * 128 + a * 64, m * 128 + warp * 16);
    };
    static_assert(((kTotalKb - kTailKb) >> 3) == 14 && kTotalKb == 120, "tail parity");
    auto tail_wait = [&](int i) { mbar_wait_n(bar_full + 8 * (i & 7), 0, retries); };
    if (wg == 1) {
      static_for<kTotalKb - kTailKb, kTotalKb>([&](auto ic) {
        constexpr int i = decltype(ic)::v, o = kb_lo(i, X) * 1024, op = kb_lo(i - 1, X) * 1024;
        tail_wait(i);
        desc_move<i & 1, op, o>(da);
        desc_move<i & 1, op + 1024, o + 1024>(db);
        wg_fence();
#pragma unroll
        for (int q = 0; q < 4; q++) {
          if (i == kTotalKb - 1 && q == 3) asm volatile("bar.arrive 2, 256;" ::: "memory");
          wgmma_n128(B, da + 2 * q, db + 128 * q, 1);
        }
      });
      wg_commit();
      wg_wait<0>();
      pin(B);
      out_half(0, B);
      out_half(1, B + 32);
    } else {
      uint32_t fr[4 * kTailRs + 1][4];
      float C0[32], C1[32];
#pragma unroll
      for (int i = 0; i < 32; i++) C0[i] = C1[i] = 0.f;
#pragma unroll
      for (int i = kTotalKb - kTailKb; i < kTotalKb; i++) {
        tail_wait(i);
        if (i >= kTotalKb - kTailRs) {
#pragma unroll
          for (int q = 0; q < 4; q++) ldsm4(fr[(i - kTotalKb + kTailRs) * 4 + q], ((stg_lane - kRing) ^ (q << 5)) + kb_off<X>(i));
        }
      }
      asm volatile("bar.sync 2, 256;" ::: "memory");
      wg_fence();
      auto rel = [](int i) { return (int64_t)(kb_off<X>(i) >> 4) - (int64_t)(kb_off<X>(kTotalKb - kTailKb - 1) >> 4); };
#pragma unroll
      for (int q = 0; q < 4 * (kTailKb - kTailRs); q++)
        wgmma_n128(B, da + (rel(kTotalKb - kTailKb + (q >> 2)) + 2 * (q & 3)), db + (rel(kTotalKb - kTailKb + (q >> 2)) + 128 * (q & 3)), 1);
      wg_commit();
#pragma unroll
      for (int q = 0; q < 4 * kTailRs; q++)
        wgmma_rs_n64(C0, fr[q], db + (rel(kTotalKb - kTailRs + (q >> 2)) + 128 * (q & 3)), q != 0);
      wg_commit();
      wg_wait<1>();
      pin(B);
#pragma unroll
      for (int i = 0; i < 32; i++) C1[i] = __fadd_rn(B[32 + i], 0.f);
      pin(C1);
      wg_fence();
#pragma unroll
      for (int q = 0; q < 4 * kTailRs; q++)
        wgmma_rs_n64(C1, fr[q], db + (rel(kTotalKb - kTailRs + (q >> 2)) + 512 + 128 * (q & 3)), 1);
      wg_commit();
      wg_wait<1>();
      pin(C0);
      if (always) {
#pragma unroll
        for (int i = 0; i < 32; i++) C0[i] += B[i];
        out_half(0, C0);
      }
      wg_wait<0>();
      pin(C1);
      out_half(1, C1);
    }
    if (lane == 0) { bulk_commit(); bulk_wait_read(); }
  }
}

typedef CUresult (*EncodeFn)(CUtensorMap*, CUtensorMapDataType, cuuint32_t, void*, const cuuint64_t*, const cuuint64_t*,
                             const cuuint32_t*, const cuuint32_t*, CUtensorMapInterleave, CUtensorMapSwizzle,
                             CUtensorMapL2promotion, CUtensorMapFloatOOBfill);

CUtensorMap make_map(EncodeFn fn, void* ptr, uint64_t d0, uint64_t d1, uint64_t d2, uint64_t s1, uint64_t s2,
                     uint32_t b0, uint32_t b1, uint32_t b2) {
  CUtensorMap m;
  cuuint64_t dims[3] = {d0, d1, d2}, strides[2] = {s1, s2};
  cuuint32_t box[3] = {b0, b1, b2}, es[3] = {1, 1, 1};
  CUresult e = fn(&m, CU_TENSOR_MAP_DATA_TYPE_BFLOAT16, d2 ? 3 : 2, ptr, dims, strides, box, es, CU_TENSOR_MAP_INTERLEAVE_NONE,
     CU_TENSOR_MAP_SWIZZLE_128B, CU_TENSOR_MAP_L2_PROMOTION_L2_128B, CU_TENSOR_MAP_FLOAT_OOB_FILL_NONE);
  return m;
}

}

extern "C" void kernel_launch(void* const* d_in, const int* in_sizes, int n_in, void* d_out, int out_size) {
  static EncodeFn fn = nullptr;
  static void *ph, *pf;
  static int clusters = 0;
  if (!fn) {
    cudaGetSymbolAddress(&ph, g_h);
    cudaGetSymbolAddress(&pf, g_flag);
    cudaDriverEntryPointQueryResult st;
    cudaGetDriverEntryPoint("cuTensorMapEncodeTiled", (void**)&fn, cudaEnableDefault, &st);
    cudaFuncSetAttribute(geglu_ffn_kernel<true>, cudaFuncAttributeMaxDynamicSharedMemorySize, kSmemBytes);
    cudaFuncSetAttribute(geglu_ffn_kernel<false>, cudaFuncAttributeMaxDynamicSharedMemorySize, kSmemBytes);
    cudaLaunchConfig_t cfg = {};
    cfg.gridDim = dim3(132);
    cfg.blockDim = dim3(384);
    cfg.dynamicSmemBytes = kSmemBytes;
    if (cudaOccupancyMaxActiveClusters(&clusters, geglu_ffn_kernel<true>, &cfg) != cudaSuccess) {
      clusters = 0;
      cudaGetLastError();
    }
  }
  uint8_t *g = (uint8_t*)d_in[1], *u = (uint8_t*)d_in[2], *h = (uint8_t*)ph;
  constexpr int kRows = 16 * kAtoms * 128;
  Maps tm;
  tm.x = make_map(fn, d_in[0], kD, kM, 0, kD * 2, 0, 64, 128, 1);
  tm.g = make_map(fn, g, 64, kD, kAtoms, kF * 2, 128, 64, 64, 2);
  tm.u = make_map(fn, u, 64, kD, kAtoms, kF * 2, 128, 64, 64, 2);
  tm.g1 = make_map(fn, g, kF, kD, 0, kF * 2, 0, 64, 64, 1);
  tm.u1 = make_map(fn, u, kF, kD, 0, kF * 2, 0, 64, 64, 1);
  tm.d = make_map(fn, d_in[3], 64, kF, kD / 64, kD * 2, 128, 64, 64, 2);
  tm.d1 = make_map(fn, d_in[3], kD, kF, 0, kD * 2, 0, 64, 64, 1);
  tm.o = make_map(fn, d_out, kD, kM, 0, kD * 2, 0, 64, 16, 1);
  tm.g48 = make_map(fn, g, kF, kD, 0, kF * 2, 0, 48, 64, 1);
  tm.u48 = make_map(fn, u, kF, kD, 0, kF * 2, 0, 48, 64, 1);
  tm.d48 = make_map(fn, d_in[3], kD, kF, 0, kD * 2, 0, 64, 48, 1);
  tm.d16 = make_map(fn, d_in[3], kD, kF, 0, kD * 2, 0, 64, 16, 1);
  tm.hl = make_map(fn, h, 64, kRows, 0, 128, 0, 64, 128, 1);
  tm.hs = make_map(fn, h, 64, kRows, 0, 128, 0, 48, 32, 1);
  const bool wide = clusters >= 66;
  (wide ? geglu_ffn_kernel<true> : geglu_ffn_kernel<false>)<<<wide ? 132 : 128, 384, kSmemBytes>>>((const uint8_t*)d_in[0], g, u, h, (uint32_t*)pf,
                                             tm);
}
```
